```python
import torch

def _softmax(x, axis=-1):
    return torch.softmax(x, dim=axis)
def _gelu(x):
    return torch.nn.functional.gelu(x, approximate="tanh")
def _silu(x):
    return torch.nn.functional.silu(x)
def _sigmoid(x):
    return torch.sigmoid(x)
def _layernorm(x, axis=-1, eps=1e-5):
    m = x.mean(dim=axis, keepdim=True)
    v = x.var(dim=axis, keepdim=True, unbiased=False)
    return (x - m) / torch.sqrt(v + eps)
def _scatter_add(tgt, idx, src, axis=0):
    return tgt.clone().index_add_(axis, idx, src)
def _segment_sum(src, seg, n):
    out = torch.zeros((n,) + src.shape[1:], dtype=src.dtype)
    return out.index_add_(0, seg, src)
def _pad(x, pw):
    flat = tuple(v for pair in reversed(pw) for v in pair)
    return torch.nn.functional.pad(x, flat)

kernel_name = 'parallel_sum__mha_block_cached__dense_activation_silu__decode'

def setup_inputs():

    _w = (lambda a: (lambda t: t.to(torch.bfloat16) if t.is_floating_point() else t)(torch.as_tensor(a)))
    def _A_setup():
        B, Sq, D = 8, 1, 448
        H, Sk, Dh = 16, 4096, 256
        return {
            "x": _w((lambda *s: torch.randn(*s, dtype=torch.bfloat16) * 0.05)(B, Sq, D)),
            "k_cache": _w((lambda *s: torch.randn(*s, dtype=torch.bfloat16) * 3.2)(B, H, Sk, Dh)),
            "v_cache": _w((lambda *s: torch.randn(*s, dtype=torch.bfloat16) * 0.8)(B, H, Sk, Dh)),
            "wq": _w((lambda *s: torch.randn(*s, dtype=torch.bfloat16) * 3.2)(D, H * Dh) * (D ** -0.5)),
            "wo": _w((lambda *s: torch.randn(*s, dtype=torch.bfloat16) * 0.8)(H * Dh, D) * ((H * Dh) ** -0.5)),
        }
    _A_in = _A_setup()

    def _B_setup():
        B, S, D, F = 8, 1, 448, 1792
        return {
            "x": _w((lambda *s: torch.randn(*s, dtype=torch.bfloat16) * 0.05)(B, S, D)),
            "w1": _w((lambda *s: torch.randn(*s, dtype=torch.bfloat16) * 3.2)(D, F) * (D ** -0.5)),
            "w2": _w((lambda *s: torch.randn(*s, dtype=torch.bfloat16) * 0.4)(F, D) * (F ** -0.5)),
        }
    _B_in = _B_setup()

    return {
        "A_x": _A_in["x"],
        "A_k_cache": _A_in["k_cache"],
        "A_v_cache": _A_in["v_cache"],
        "A_wq": _A_in["wq"],
        "A_wo": _A_in["wo"],
        "B_x": _B_in["x"],
        "B_w1": _B_in["w1"],
        "B_w2": _B_in["w2"],
    }

def reference(A_x, A_k_cache, A_v_cache, A_wq, A_wo, B_x, B_w1, B_w2):
    def _A_ref(x, k_cache, v_cache, wq, wo):
        B, Sq, D = x.shape
        H, Dh = 16, 256
        q = (lambda x, *d: x.permute(*d))((x @ wq).reshape(B, Sq, H, Dh), 0, 2, 1, 3)
        scores = torch.einsum("bhqd,bhkd->bhqk", q, k_cache) * (Dh ** -0.5)
        p = _softmax(scores, axis=-1)
        o = torch.einsum("bhqk,bhkd->bhqd", p, v_cache)
        return (lambda x, *d: x.permute(*d))(o, 0, 2, 1, 3).reshape(B, Sq, H * Dh) @ wo

    def _B_ref(x, w1, w2):
        h = torch.einsum("bsd,df->bsf", x, w1)
        h = _silu(h)
        out = torch.einsum("bsf,fd->bsd", h, w2)
        return out

    x = A_x
    xn = _layernorm(x, axis=-1)
    return x + _A_ref(xn, A_k_cache, A_v_cache, A_wq, A_wo) + _B_ref(xn, B_w1, B_w2)
```

```cpp
#include <cuda_runtime.h>
#include <cuda_bf16.h>
#include <stdint.h>

namespace {

constexpr int NB = 8, NH = 16, SK = 4096, DH = 256, DM = 448, FF = 1792;
constexpr int NBH = NB * NH;
constexpr int TILE_BYTES = 32768;
constexpr int UNITS_PER_BH = 32;
constexpr int NKU = NBH * UNITS_PER_BH;
constexpr int NUNITS = 2 * NKU;
constexpr int GRID = 132;
constexpr int NSLOT = 5;
#define CAP 2
constexpr int NWORK = 112;
constexpr int NHSL = FF / 32;
constexpr int NTHREADS = 13 * 32;
constexpr int XN_PITCH = 456;

constexpr int SM_RING = 0;
constexpr int SM_SIDE = SM_RING + NSLOT * TILE_BYTES;
constexpr int SM_STAGE = SM_SIDE + NSLOT * 1024;
constexpr int SM_WO = SM_STAGE + 4 * 1024;
constexpr int SM_XN = SM_WO + 32768;
constexpr int SM_MISC = SM_XN + NB * XN_PITCH * 2;
constexpr int SM_TOTAL = SM_MISC + 2048;

struct Misc {
    unsigned long long full[NSLOT];
    unsigned long long empty[NSLOT];
    int desc[NSLOT];
    int progress;
    unsigned tag;
    float hred[2][4];
    float fpart[4][32];
    float apart[2][4][4];
};

__device__ unsigned g_ticket;
__device__ unsigned g_epoch;
__device__ __align__(128) unsigned g_q[NBH * DH];
__device__ __align__(128) unsigned g_h[FF * NB];
__device__ __align__(128) unsigned g_sp[NBH * SK];
__device__ __align__(128) unsigned g_rec[NKU * DH];
__device__ __align__(128) unsigned g_o[NBH * DH];

__device__ __forceinline__ uint32_t smem_u32(const void* p) { return (uint32_t)__cvta_generic_to_shared(p); }
__device__ __forceinline__ void mbar_init(uint32_t bar, uint32_t cnt) {
    asm volatile("mbarrier.init.shared::cta.b64 [%0], %1;" ::"r"(bar), "r"(cnt) : "memory");
}
__device__ __forceinline__ void mbar_expect_tx(uint32_t bar, uint32_t bytes) {
    asm volatile("mbarrier.arrive.expect_tx.shared::cta.b64 _, [%0], %1;" ::"r"(bar), "r"(bytes) : "memory");
}
__device__ __forceinline__ void mbar_arrive(uint32_t bar) {
    asm volatile("mbarrier.arrive.shared::cta.b64 _, [%0];" ::"r"(bar) : "memory");
}
__device__ __forceinline__ bool mbar_try(uint32_t bar, uint32_t parity) {
    uint32_t done;
    asm volatile("{\n.reg .pred p;\nmbarrier.try_wait.parity.shared::cta.b64 p, [%1], %2;\nselp.u32 %0, 1, 0, p;\n}"
                 : "=r"(done) : "r"(bar), "r"(parity) : "memory");
    return done != 0;
}
constexpr long long SPIN_LIMIT = 4000000000LL;
struct Watchdog {
    long long t0;
    __device__ __forceinline__ Watchdog() { t0 = clock64(); }
    __device__ __forceinline__ void check() { if (clock64() - t0 > SPIN_LIMIT) __trap(); }
};
__device__ __forceinline__ void mbar_wait(uint32_t bar, uint32_t parity) {
    if (mbar_try(bar, parity)) return;
    Watchdog wd;
    while (!mbar_try(bar, parity)) wd.check();
}
__device__ __forceinline__ void bulk_load(uint32_t dst, const void* src, uint32_t bytes, uint32_t bar) {
    asm volatile("cp.async.bulk.shared::cluster.global.mbarrier::complete_tx::bytes [%0], [%1], %2, [%3];"
                 ::"r"(dst), "l"(src), "r"(bytes), "r"(bar) : "memory");
}
__device__ __forceinline__ void bulk_load_hint(uint32_t dst, const void* src, uint32_t bytes, uint32_t bar, uint64_t pol) {
    asm volatile("cp.async.bulk.shared::cluster.global.mbarrier::complete_tx::bytes.L2::cache_hint [%0], [%1], %2, [%3], %4;"
                 ::"r"(dst), "l"(src), "r"(bytes), "r"(bar), "l"(pol) : "memory");
}
__device__ __forceinline__ void bar_sync(int id, int n) { asm volatile("bar.sync %0, %1;" ::"r"(id), "r"(n) : "memory"); }
__device__ __forceinline__ uint4 lds128(uint32_t a) {
    uint4 v;
    asm volatile("ld.shared.v4.u32 {%0,%1,%2,%3}, [%4];" : "=r"(v.x), "=r"(v.y), "=r"(v.z), "=r"(v.w) : "r"(a));
    return v;
}
__device__ __forceinline__ uint2 lds64(uint32_t a) {
    uint2 v;
    asm volatile("ld.shared.v2.u32 {%0,%1}, [%2];" : "=r"(v.x), "=r"(v.y) : "r"(a));
    return v;
}
__device__ __forceinline__ uint32_t lds32(uint32_t a) {
    uint32_t v;
    asm volatile("ld.shared.u32 %0, [%1];" : "=r"(v) : "r"(a));
    return v;
}
__device__ __forceinline__ void sts128(uint32_t a, uint4 v) {
    asm volatile("st.shared.v4.u32 [%0], {%1,%2,%3,%4};" ::"r"(a), "r"(v.x), "r"(v.y), "r"(v.z), "r"(v.w) : "memory");
}
__device__ __forceinline__ void ldsm4t(uint32_t (&r)[4], uint32_t a) {
    asm volatile("ldmatrix.sync.aligned.m8n8.x4.trans.shared.b16 {%0,%1,%2,%3}, [%4];"
                 : "=r"(r[0]), "=r"(r[1]), "=r"(r[2]), "=r"(r[3]) : "r"(a));
}
__device__ __forceinline__ void mma16816(float (&d)[4], uint32_t a0, uint32_t a1, uint32_t a2, uint32_t a3, uint32_t b0, uint32_t b1) {
    asm volatile("mma.sync.aligned.m16n8k16.row.col.f32.bf16.bf16.f32 {%0,%1,%2,%3}, {%4,%5,%6,%7}, {%8,%9}, {%0,%1,%2,%3};"
                 : "+f"(d[0]), "+f"(d[1]), "+f"(d[2]), "+f"(d[3]) : "r"(a0), "r"(a1), "r"(a2), "r"(a3), "r"(b0), "r"(b1));
}
__device__ __forceinline__ uint4 ldg_poll128(const unsigned* p) {
    uint4 v;
    asm volatile("ld.relaxed.gpu.global.v4.u32 {%0,%1,%2,%3}, [%4];" : "=r"(v.x), "=r"(v.y), "=r"(v.z), "=r"(v.w) : "l"(p) : "memory");
    return v;
}
__device__ __forceinline__ uint2 ldg_poll64(const unsigned* p) {
    uint2 v;
    asm volatile("ld.relaxed.gpu.global.v2.u32 {%0,%1}, [%2];" : "=r"(v.x), "=r"(v.y) : "l"(p) : "memory");
    return v;
}
__device__ __forceinline__ void stg_pub32(unsigned* p, unsigned v) {
    asm volatile("st.relaxed.gpu.global.u32 [%0], %1;" ::"l"(p), "r"(v) : "memory");
}
__device__ __forceinline__ void stg_pub64(unsigned* p, unsigned a, unsigned b) {
    asm volatile("st.relaxed.gpu.global.v2.u32 [%0], {%1,%2};" ::"l"(p), "r"(a), "r"(b) : "memory");
}
__device__ __forceinline__ void stg_pub128(unsigned* p, uint4 v) {
    asm volatile("st.relaxed.gpu.global.v4.u32 [%0], {%1,%2,%3,%4};" ::"l"(p), "r"(v.x), "r"(v.y), "r"(v.z), "r"(v.w) : "memory");
}
__device__ __forceinline__ uint2 ldg_nc64(const void* p) {
    uint2 v;
    asm volatile("ld.global.nc.v2.u32 {%0,%1}, [%2];" : "=r"(v.x), "=r"(v.y) : "l"(p));
    return v;
}
__device__ __forceinline__ unsigned bf16_bits(float f) { return (unsigned)__bfloat16_as_ushort(__float2bfloat16_rn(f)); }
__device__ __forceinline__ float bf16_round(float f) { return __uint_as_float(bf16_bits(f) << 16); }
__device__ __forceinline__ float hi_f(unsigned w) { return __uint_as_float(w & 0xffff0000u); }
__device__ __forceinline__ float lo_f(unsigned w) { return __uint_as_float(w << 16); }
__device__ __forceinline__ bool tag16_ok(uint4 v, unsigned tag) {
    return (((v.x ^ tag) | (v.y ^ tag) | (v.z ^ tag) | (v.w ^ tag)) & 0xffffu) == 0;
}
__device__ __forceinline__ bool tag2_ok(uint4 v, unsigned tag) {
    return (((v.x ^ tag) | (v.y ^ tag) | (v.z ^ tag) | (v.w ^ tag)) & 3u) == 0;
}
__device__ __forceinline__ void wait_progress(const Misc* ms, int target) {
    const volatile int* p = &ms->progress;
    if (*p >= target) return;
    Watchdog wd;
    while (*p < target) { __nanosleep(256); wd.check(); }
}

__device__ __forceinline__ void proj_load(uint2 (&w)[16], const __nv_bfloat16* W, int pitch, int col0, int aw, int g, int t) {
    const __nv_bfloat16* p = W + (size_t)(64 * aw + 2 * t) * pitch + col0 + 4 * g;
#pragma unroll
    for (int ks = 0; ks < 4; ks++) {
        w[4 * ks + 0] = ldg_nc64(p + (size_t)(16 * ks + 0) * pitch);
        w[4 * ks + 1] = ldg_nc64(p + (size_t)(16 * ks + 1) * pitch);
        w[4 * ks + 2] = ldg_nc64(p + (size_t)(16 * ks + 8) * pitch);
        w[4 * ks + 3] = ldg_nc64(p + (size_t)(16 * ks + 9) * pitch);
    }
}
__device__ __forceinline__ void proj_mma(const uint2 (&w)[16], uint32_t xn_s, uint32_t red_s, int aw, int g, int t) {
    float d0[4] = {0.f, 0.f, 0.f, 0.f}, d1[4] = {0.f, 0.f, 0.f, 0.f};
    const uint32_t xa = xn_s + (g * XN_PITCH + 64 * aw + 2 * t) * 2;
#pragma unroll
    for (int ks = 0; ks < 4; ks++) {
        const uint32_t b0 = lds32(xa + ks * 32), b1 = lds32(xa + ks * 32 + 16);
        const uint2 x = w[4 * ks], y = w[4 * ks + 1], z = w[4 * ks + 2], u = w[4 * ks + 3];
        mma16816(d0, __byte_perm(x.x, y.x, 0x5410), __byte_perm(x.x, y.x, 0x7632), __byte_perm(z.x, u.x, 0x5410), __byte_perm(z.x, u.x, 0x7632), b0, b1);
        mma16816(d1, __byte_perm(x.y, y.y, 0x5410), __byte_perm(x.y, y.y, 0x7632), __byte_perm(z.y, u.y, 0x5410), __byte_perm(z.y, u.y, 0x7632), b0, b1);
    }
    const uint32_t ra = red_s + aw * 1024 + (2 * t * 32 + 4 * g) * 4;
    sts128(ra, make_uint4(__float_as_uint(d0[0]), __float_as_uint(d0[2]), __float_as_uint(d1[0]), __float_as_uint(d1[2])));
    sts128(ra + 128, make_uint4(__float_as_uint(d0[1]), __float_as_uint(d0[3]), __float_as_uint(d1[1]), __float_as_uint(d1[3])));
}
__device__ __forceinline__ float proj_sum(uint32_t red_s, int idx) {
    float s = 0.f;
#pragma unroll
    for (int w = 0; w < 7; w++) s += __uint_as_float(lds32(red_s + w * 1024 + idx * 4));
    return s;
}

__global__ void __launch_bounds__(NTHREADS, 1)
fused_decode_kernel(const __nv_bfloat16* __restrict__ x, const char* __restrict__ Kc, const char* __restrict__ Vc,
                    const __nv_bfloat16* __restrict__ wq, const __nv_bfloat16* __restrict__ wo,
                    const __nv_bfloat16* __restrict__ w1, const __nv_bfloat16* __restrict__ w2,
                    __nv_bfloat16* __restrict__ out) {
    extern __shared__ __align__(1024) unsigned char smem[];
    Misc* ms = reinterpret_cast<Misc*>(smem + SM_MISC);
    const uint32_t sb = smem_u32(smem);
    const int warp = threadIdx.x >> 5, lane = threadIdx.x & 31;
    const int g = lane >> 2, t = lane & 3;
    const int cta = blockIdx.x;
    const uint32_t full0 = smem_u32(&ms->full[0]), empty0 = smem_u32(&ms->empty[0]);

    if (warp == 12) {
        uint64_t pol = 0;
        int unit = cta, next = 0, i = 0;
        auto issue = [&](int j, int slot) {
            ms->desc[slot] = unit * 2 + j;
            const uint32_t bar = full0 + 8 * slot;
            const uint32_t dst = sb + SM_RING + slot * TILE_BYTES, side = sb + SM_SIDE + slot * 1024;
            if (unit < NKU) {
                mbar_expect_tx(bar, TILE_BYTES + (j == 0 ? 1024 : 0));
                bulk_load_hint(dst, Kc + (size_t)(unit * 2 + j) * TILE_BYTES, TILE_BYTES, bar, pol);
                if (j == 0) bulk_load(side, g_q + (unit >> 5) * DH, 1024, bar);
            } else {
                const int vt = (unit - NKU) * 2 + j;
                mbar_expect_tx(bar, TILE_BYTES + 256);
                bulk_load_hint(dst, Vc + (size_t)vt * TILE_BYTES, TILE_BYTES, bar, pol);
                bulk_load(side, g_sp + vt * 64, 256, bar);
            }
        };
        if (lane == 0) {
            for (int s = 0; s < NSLOT; s++) { mbar_init(full0 + 8 * s, 1); mbar_init(empty0 + 8 * s, 4); }
            ms->progress = 0;
            asm volatile("fence.mbarrier_init.release.cluster;" ::: "memory");
            asm volatile("fence.proxy.async.shared::cta;" ::: "memory");
            asm volatile("createpolicy.fractional.L2::evict_first.b64 %0, 1.0;" : "=l"(pol));
            issue(0, 0);
            issue(1, 1);
            next = (int)atomicInc(&g_ticket, NUNITS - 1);
            i = 2;
        }
        __syncthreads();
        if (lane == 0) {
            int slot = 2; uint32_t eph = 1;
            int aslot = (2 - CAP + NSLOT) % NSLOT; uint32_t aph = (2 - CAP < 0) ? 1 : 0;
            unit = next + GRID;
            while (unit < NUNITS) {
                *(volatile int*)&ms->progress = unit;
#pragma unroll
                for (int j = 0; j < 2; j++) {
                    mbar_wait(empty0 + 8 * slot, eph);
                    mbar_wait(full0 + 8 * aslot, aph);
                    issue(j, slot);
                    if (j == 0) next = (int)atomicInc(&g_ticket, NUNITS - 1);
                    if (++slot == NSLOT) { slot = 0; eph ^= 1; }
                    if (++aslot == NSLOT) { aslot = 0; aph ^= 1; }
                    i++;
                }
                unit = next + GRID;
            }
            *(volatile int*)&ms->progress = 1 << 30;
            mbar_wait(empty0 + 8 * slot, eph);
            ms->desc[slot] = -1;
            mbar_arrive(full0 + 8 * slot);
        }
        return;
    }

    if (warp < 4) {
        __syncthreads();
        bar_sync(1, 384);
        const unsigned tag = ms->tag;
        const unsigned tagP = tag + 2;
        const uint32_t koffA = warp * 8192 + g * 512 + (t + 4 * (g & 1)) * 16;
        const uint32_t qoffA = (t + 4 * (g & 1)) * 32;
        const int mi = lane >> 3, r = lane & 7;
        const uint32_t voff = (r + 8 * (mi >> 1)) * 512 + 128 * warp + (((mi & 1) ^ r) * 16);
        const uint32_t psel = (t == (g >> 1)) ? ((g & 1) ? 0x3244u : 0x4432u) : 0x4444u;
        const uint32_t stage = sb + SM_STAGE + warp * 1024;
        uint32_t Q[32];
        float acc[4][4];
        int slot = 0; uint32_t ph = 0;
        while (true) {
            mbar_wait(full0 + 8 * slot, ph);
            const int d = *(volatile int*)&ms->desc[slot];
            if (d < 0) break;
            const uint32_t tile = sb + SM_RING + slot * TILE_BYTES;
            uint32_t side = sb + SM_SIDE + slot * 1024;
            if (d < 2 * NKU) {
                if ((d & 1) == 0) {
                    const uint4 c0 = lds128(side + lane * 16), c1 = lds128(side + 512 + lane * 16);
                    if (!__all_sync(0xffffffffu, tag16_ok(c0, tag) && tag16_ok(c1, tag))) {
                        const unsigned* src = g_q + (d >> 6) * DH + lane * 4;
                        Watchdog wd;
                        uint4 a, b;
                        while (true) {
                            a = ldg_poll128(src); b = ldg_poll128(src + 128);
                            if (__all_sync(0xffffffffu, tag16_ok(a, tag) && tag16_ok(b, tag))) break;
                            __nanosleep(100); wd.check();
                        }
                        sts128(stage + lane * 16, a); sts128(stage + 512 + lane * 16, b);
                        __syncwarp();
                        side = stage;
                    }
#pragma unroll
                    for (int j = 0; j < 4; j++) {
#pragma unroll
                        for (int u = 0; u < 2; u++) {
                            const uint32_t a = side + ((qoffA ^ (u * 128)) + j * 256);
                            const uint4 lo = lds128(a), hi = lds128(a + 16);
                            Q[8 * j + 4 * u + 0] = __byte_perm(lo.x, lo.y, 0x7632);
                            Q[8 * j + 4 * u + 1] = __byte_perm(lo.z, lo.w, 0x7632);
                            Q[8 * j + 4 * u + 2] = __byte_perm(hi.x, hi.y, 0x7632);
                            Q[8 * j + 4 * u + 3] = __byte_perm(hi.z, hi.w, 0x7632);
                        }
                    }
                }
                float d0[4] = {0.f, 0.f, 0.f, 0.f}, d1[4] = {0.f, 0.f, 0.f, 0.f};
                float d2[4] = {0.f, 0.f, 0.f, 0.f}, d3[4] = {0.f, 0.f, 0.f, 0.f};
                const uint32_t ka = tile + koffA, kb = tile + (koffA ^ 64);
#pragma unroll
                for (int j = 0; j < 4; j++) {
                    const uint4 X = lds128(ka + j * 128), Y = lds128(ka + j * 128 + 4096);
                    const uint4 Z = lds128(kb + j * 128), W = lds128(kb + j * 128 + 4096);
                    mma16816(d0, X.x, Y.x, X.y, Y.y, Q[8 * j + 0], Q[8 * j + 1]);
                    mma16816(d1, X.z, Y.z, X.w, Y.w, Q[8 * j + 2], Q[8 * j + 3]);
                    mma16816(d2, Z.x, W.x, Z.y, W.y, Q[8 * j + 4], Q[8 * j + 5]);
                    mma16816(d3, Z.z, W.z, Z.w, W.w, Q[8 * j + 6], Q[8 * j + 7]);
                }
                __syncwarp();
                if (lane == 0) mbar_arrive(empty0 + 8 * slot);
                float s[4];
#pragma unroll
                for (int e = 0; e < 4; e++) s[e] = (d0[e] + d1[e]) + (d2[e] + d3[e]);
                const float slo = (g & 1) ? s[1] : s[0], shi = (g & 1) ? s[3] : s[2];
                if (t < 2) stg_pub32(g_sp + d * 64 + 16 * warp + 8 * t + g, (bf16_bits(t ? shi : slo) << 16) | tag);
            } else {
                const int vt = d - 2 * NKU;
                {
                    const uint2 c = lds64(side + lane * 8);
                    if (!__all_sync(0xffffffffu, (((c.x ^ tagP) | (c.y ^ tagP)) & 0xffffu) == 0)) {
                        const unsigned* src = g_sp + vt * 64 + lane * 2;
                        Watchdog wd;
                        uint2 a;
                        while (true) {
                            a = ldg_poll64(src);
                            if (__all_sync(0xffffffffu, (((a.x ^ tagP) | (a.y ^ tagP)) & 0xffffu) == 0)) break;
                            __nanosleep(100); wd.check();
                        }
                        asm volatile("st.shared.v2.u32 [%0], {%1,%2};" ::"r"(stage + lane * 8), "r"(a.x), "r"(a.y) : "memory");
                        __syncwarp();
                        side = stage;
                    }
                }
                if ((vt & 1) == 0) {
#pragma unroll
                    for (int i = 0; i < 4; i++)
#pragma unroll
                        for (int e = 0; e < 4; e++) acc[i][e] = 0.f;
                }
                const uint32_t va = tile + voff;
#pragma unroll
                for (int kg = 0; kg < 4; kg++) {
                    const uint32_t b0 = __byte_perm(lds32(side + (16 * kg + g) * 4), 0, psel);
                    const uint32_t b1 = __byte_perm(lds32(side + (16 * kg + 8 + g) * 4), 0, psel);
#pragma unroll
                    for (int i = 0; i < 4; i++) {
                        uint32_t a[4];
                        ldsm4t(a, (va ^ (32 * i)) + kg * 8192);
                        mma16816(acc[i], a[0], a[1], a[2], a[3], b0, b1);
                    }
                }
                __syncwarp();
                if (lane == 0) mbar_arrive(empty0 + 8 * slot);
                if (vt & 1) {
                    float e0[4], e1[4];
#pragma unroll
                    for (int i = 0; i < 4; i++) { e0[i] = acc[i][0] + acc[i][3]; e1[i] = acc[i][1] + acc[i][2]; }
                    e0[0] += __shfl_xor_sync(0xffffffffu, e0[1], 1);
                    e1[0] += __shfl_xor_sync(0xffffffffu, e1[1], 1);
                    e0[2] += __shfl_xor_sync(0xffffffffu, e0[3], 1);
                    e1[2] += __shfl_xor_sync(0xffffffffu, e1[3], 1);
                    e0[0] += __shfl_xor_sync(0xffffffffu, e0[2], 2);
                    e1[0] += __shfl_xor_sync(0xffffffffu, e1[2], 2);
                    stg_pub64(g_rec + (size_t)(vt >> 1) * DH + 64 * warp + 2 * lane,
                              (__float_as_uint(e0[0]) & ~3u) | tag, (__float_as_uint(e1[0]) & ~3u) | tag);
                }
            }
            if (++slot == NSLOT) { slot = 0; ph ^= 1; }
        }
        return;
    }

    const int aw = warp - 4;
    const int at = threadIdx.x - 128;
    const uint32_t xn_s = sb + SM_XN, red_s = sb + SM_WO;
    uint2 wf[16];
    if (cta < NBH && aw < 7) proj_load(wf, wq, NH * DH, 32 * cta, aw, g, t);
    {
        const unsigned* xr = reinterpret_cast<const unsigned*>(x + aw * DM);
        unsigned xv[7];
#pragma unroll
        for (int i = 0; i < 7; i++) xv[i] = __ldg(xr + lane + 32 * i);
        unsigned ep = 0;
        if (at == 255) ep = atomicInc(&g_epoch, 2 * GRID - 1);
        __syncthreads();
        float s = 0.f;
#pragma unroll
        for (int i = 0; i < 7; i++) s += lo_f(xv[i]) + hi_f(xv[i]);
#pragma unroll
        for (int o = 16; o; o >>= 1) s += __shfl_xor_sync(0xffffffffu, s, o);
        const float mean = s * (1.0f / DM);
        float v = 0.f;
#pragma unroll
        for (int i = 0; i < 7; i++) {
            const float a = lo_f(xv[i]) - mean, b = hi_f(xv[i]) - mean;
            v += a * a + b * b;
        }
#pragma unroll
        for (int o = 16; o; o >>= 1) v += __shfl_xor_sync(0xffffffffu, v, o);
        const float mb = bf16_round(mean);
        const float den = bf16_round(sqrtf(bf16_round(bf16_round(v * (1.0f / DM)) + 1e-5f)));
#pragma unroll
        for (int i = 0; i < 7; i++) {
            const unsigned a = bf16_bits(bf16_round(lo_f(xv[i]) - mb) / den);
            const unsigned b = bf16_bits(bf16_round(hi_f(xv[i]) - mb) / den);
            asm volatile("st.shared.u32 [%0], %1;" ::"r"(xn_s + aw * XN_PITCH * 2 + (lane + 32 * i) * 4), "r"(a | (b << 16)) : "memory");
        }
        if (at == 255) ms->tag = ep >= GRID ? 2u : 1u;
    }
    bar_sync(1, 384);
    const unsigned tag = ms->tag;
    if (cta < NBH) {
        if (aw < 7) proj_mma(wf, xn_s, red_s, aw, g, t);
        bar_sync(2, 256);
        const float qv = proj_sum(red_s, at);
        stg_pub32(g_q + aw * (NH * DH) + 32 * cta + lane, (bf16_bits(qv) << 16) | tag);
    }
    if (cta >= GRID - NHSL) {
        const int hs = cta - (GRID - NHSL);
        if (aw < 7) proj_load(wf, w1, FF, 32 * hs, aw, g, t);
        bar_sync(2, 256);
        if (aw < 7) proj_mma(wf, xn_s, red_s, aw, g, t);
        bar_sync(2, 256);
        const float hv = bf16_round(proj_sum(red_s, (at & 7) * 32 + (at >> 3)));
        const float sv = hv / (1.0f + __expf(-hv));
        stg_pub32(g_h + 256 * hs + at, (bf16_bits(sv) << 16) | tag);
    }
    bar_sync(2, 256);

    if (aw < 4) {
        if (cta >= NBH) return;
        const int bh = cta;
        {
            wait_progress(ms, (bh + 1) * UNITS_PER_BH + 2 * GRID);
            unsigned* sp = g_sp + bh * SK + at * 4;
            uint4 v[8];
#pragma unroll
            for (int i = 0; i < 8; i++) v[i] = ldg_poll128(sp + i * 512);
            Watchdog wd;
            while (true) {
                bool ok = true;
#pragma unroll
                for (int i = 0; i < 8; i++) ok = ok && tag16_ok(v[i], tag);
                if (ok) break;
                __nanosleep(200); wd.check();
#pragma unroll
                for (int i = 0; i < 8; i++) if (!tag16_ok(v[i], tag)) v[i] = ldg_poll128(sp + i * 512);
            }
            float m = -INFINITY;
#pragma unroll
            for (int i = 0; i < 8; i++) m = fmaxf(fmaxf(fmaxf(m, hi_f(v[i].x)), fmaxf(hi_f(v[i].y), hi_f(v[i].z))), hi_f(v[i].w));
#pragma unroll
            for (int o = 16; o; o >>= 1) m = fmaxf(m, __shfl_xor_sync(0xffffffffu, m, o));
            if (lane == 0) ms->hred[0][aw] = m;
            bar_sync(3, 128);
            m = fmaxf(fmaxf(ms->hred[0][0], ms->hred[0][1]), fmaxf(ms->hred[0][2], ms->hred[0][3]));
            const float sc = 0.0625f * 1.4426950408889634f;
            float e[32], sum = 0.f;
#pragma unroll
            for (int i = 0; i < 8; i++) {
                e[4 * i + 0] = exp2f((hi_f(v[i].x) - m) * sc);
                e[4 * i + 1] = exp2f((hi_f(v[i].y) - m) * sc);
                e[4 * i + 2] = exp2f((hi_f(v[i].z) - m) * sc);
                e[4 * i + 3] = exp2f((hi_f(v[i].w) - m) * sc);
                sum += (e[4 * i] + e[4 * i + 1]) + (e[4 * i + 2] + e[4 * i + 3]);
            }
#pragma unroll
            for (int o = 16; o; o >>= 1) sum += __shfl_xor_sync(0xffffffffu, sum, o);
            if (lane == 0) ms->hred[1][aw] = sum;
            bar_sync(3, 128);
            sum = (ms->hred[1][0] + ms->hred[1][1]) + (ms->hred[1][2] + ms->hred[1][3]);
            const float inv = 1.0f / sum;
            const unsigned tagP = tag + 2;
#pragma unroll
            for (int i = 0; i < 8; i++)
                stg_pub128(sp + i * 512, make_uint4((bf16_bits(e[4 * i] * inv) << 16) | tagP, (bf16_bits(e[4 * i + 1] * inv) << 16) | tagP,
                                                    (bf16_bits(e[4 * i + 2] * inv) << 16) | tagP, (bf16_bits(e[4 * i + 3] * inv) << 16) | tagP));
        }
        {
            wait_progress(ms, NKU + (bh + 1) * UNITS_PER_BH);
            const unsigned* rp = g_rec + (size_t)(bh * UNITS_PER_BH + (lane >> 4) * 16) * DH + 64 * aw + 4 * (lane & 15);
            uint4 v[16];
#pragma unroll
            for (int i = 0; i < 16; i++) v[i] = ldg_poll128(rp + i * DH);
            Watchdog wd;
            while (true) {
                bool ok = true;
#pragma unroll
                for (int i = 0; i < 16; i++) ok = ok && tag2_ok(v[i], tag);
                if (ok) break;
                wd.check();
#pragma unroll
                for (int i = 0; i < 16; i++) if (!tag2_ok(v[i], tag)) v[i] = ldg_poll128(rp + i * DH);
            }
            float s0 = 0.f, s1 = 0.f, s2 = 0.f, s3 = 0.f;
#pragma unroll
            for (int i = 0; i < 16; i++) {
                s0 += __uint_as_float(v[i].x & ~3u); s1 += __uint_as_float(v[i].y & ~3u);
                s2 += __uint_as_float(v[i].z & ~3u); s3 += __uint_as_float(v[i].w & ~3u);
            }
            __syncwarp();
            s0 += __shfl_xor_sync(0xffffffffu, s0, 16); s1 += __shfl_xor_sync(0xffffffffu, s1, 16);
            s2 += __shfl_xor_sync(0xffffffffu, s2, 16); s3 += __shfl_xor_sync(0xffffffffu, s3, 16);
            if (lane < 16)
                stg_pub128(g_o + bh * DH + 64 * aw + 4 * lane,
                           make_uint4((bf16_bits(s0) << 16) | tag, (bf16_bits(s1) << 16) | tag, (bf16_bits(s2) << 16) | tag, (bf16_bits(s3) << 16) | tag));
        }
        return;
    }

    if (cta >= NWORK) return;
    {
        const int ww = aw - 4, wt = at - 128;
        const int c0 = 4 * cta;
        const uint32_t wo_s = sb + SM_WO;
#pragma unroll 4
        for (int i = 0; i < 32; i++) {
            const int idx = wt + 128 * i;
            const int row = (idx & ~63) | (((idx >> 1) & 3) << 4) | ((idx & 1) << 3) | ((idx >> 3) & 7);
            asm volatile("cp.async.ca.shared.global [%0], [%1], 8;" ::"r"(wo_s + idx * 8), "l"(wo + (size_t)row * DM + c0) : "memory");
        }
        asm volatile("cp.async.commit_group;" ::: "memory");
        {
            float fa[32];
#pragma unroll
            for (int i = 0; i < 32; i++) fa[i] = 0.f;
            Watchdog wd;
#pragma unroll 2
            for (int i = 0; i < 14; i++) {
                const int f = 448 * ww + lane + 32 * i;
                const uint2 w = ldg_nc64(w2 + (size_t)f * DM + c0);
                uint4 ha = ldg_poll128(g_h + f * 8), hb = ldg_poll128(g_h + f * 8 + 4);
                while (!(tag16_ok(ha, tag) && tag16_ok(hb, tag))) {
                    __nanosleep(500); wd.check();
                    ha = ldg_poll128(g_h + f * 8); hb = ldg_poll128(g_h + f * 8 + 4);
                }
                const float wv[4] = {lo_f(w.x), hi_f(w.x), lo_f(w.y), hi_f(w.y)};
                const float hv[8] = {hi_f(ha.x), hi_f(ha.y), hi_f(ha.z), hi_f(ha.w), hi_f(hb.x), hi_f(hb.y), hi_f(hb.z), hi_f(hb.w)};
#pragma unroll
                for (int b = 0; b < 8; b++)
#pragma unroll
                    for (int c = 0; c < 4; c++) fa[4 * b + c] = fmaf(hv[b], wv[c], fa[4 * b + c]);
            }
            __syncwarp();
#pragma unroll
            for (int st = 0; st < 5; st++) {
                const int o = 16 >> st;
                const bool up = (lane & o) != 0;
#pragma unroll
                for (int i = 0; i < 16; i++) {
                    if (i < o) {
                        const float send = up ? fa[i] : fa[i + o];
                        const float keep = up ? fa[i + o] : fa[i];
                        fa[i] = keep + __shfl_xor_sync(0xffffffffu, send, o);
                    }
                }
            }
            ms->fpart[ww][lane] = fa[0];
        }
        asm volatile("cp.async.wait_group 0;" ::: "memory");
        bar_sync(4, 128);
        float base_x = 0.f, base_f = 0.f;
        if (ww == 0) {
            base_f = bf16_round((ms->fpart[0][lane] + ms->fpart[1][lane]) + (ms->fpart[2][lane] + ms->fpart[3][lane]));
            base_x = __bfloat162float(x[g * DM + c0 + t]);
        }
        for (int b = 0; b < NB; b++) {
            float a0 = 0.f, a1 = 0.f, a2 = 0.f, a3 = 0.f;
            for (int hh = 0; hh < 4; hh++) {
                const int h = 4 * hh + ww, bh = b * NH + h;
                wait_progress(ms, NKU + (bh + 1) * UNITS_PER_BH + 3 * GRID);
                const unsigned* op = g_o + bh * DH + 4 * lane;
                uint4 oa = ldg_poll128(op), ob = ldg_poll128(op + 128);
                const uint32_t wa = wo_s + (h * 256 + 4 * lane) * 8;
                const uint4 w0 = lds128(wa), w1v = lds128(wa + 16), w2v = lds128(wa + 1024), w3 = lds128(wa + 1040);
                if (!(tag16_ok(oa, tag) && tag16_ok(ob, tag))) {
                    Watchdog wd;
                    do {
                        __nanosleep(64); wd.check();
                        if (!tag16_ok(oa, tag)) oa = ldg_poll128(op);
                        if (!tag16_ok(ob, tag)) ob = ldg_poll128(op + 128);
                    } while (!(tag16_ok(oa, tag) && tag16_ok(ob, tag)));
                }
#define WACC(o, lo, hi) { const float ov = hi_f(o); a0 = fmaf(ov, lo_f(lo), a0); a1 = fmaf(ov, hi_f(lo), a1); a2 = fmaf(ov, lo_f(hi), a2); a3 = fmaf(ov, hi_f(hi), a3); }
                WACC(oa.x, w0.x, w0.y) WACC(oa.y, w0.z, w0.w) WACC(oa.z, w1v.x, w1v.y) WACC(oa.w, w1v.z, w1v.w)
                WACC(ob.x, w2v.x, w2v.y) WACC(ob.y, w2v.z, w2v.w) WACC(ob.z, w3.x, w3.y) WACC(ob.w, w3.z, w3.w)
#undef WACC
            }
            __syncwarp();
            {
                const bool up1 = lane & 1, up2 = lane & 2;
                float k0 = up1 ? a1 : a0, k1 = up1 ? a3 : a2;
                k0 += __shfl_xor_sync(0xffffffffu, up1 ? a0 : a1, 1);
                k1 += __shfl_xor_sync(0xffffffffu, up1 ? a2 : a3, 1);
                float k = up2 ? k1 : k0;
                k += __shfl_xor_sync(0xffffffffu, up2 ? k0 : k1, 2);
                k += __shfl_xor_sync(0xffffffffu, k, 4);
                k += __shfl_xor_sync(0xffffffffu, k, 8);
                k += __shfl_xor_sync(0xffffffffu, k, 16);
                if (lane < 4) ms->apart[b & 1][ww][lane] = k;
            }
            bar_sync(4, 128);
            if (ww == 0 && g == b) {
                const float at4 = (ms->apart[b & 1][0][t] + ms->apart[b & 1][1][t]) + (ms->apart[b & 1][2][t] + ms->apart[b & 1][3][t]);
                out[b * DM + c0 + t] = __float2bfloat16_rn(bf16_round(base_x + bf16_round(at4)) + base_f);
            }
        }
    }
}

}

extern "C" void kernel_launch(void* const* d_in, const int* in_sizes, int n_in, void* d_out, int out_size) {
    (void)in_sizes; (void)n_in; (void)out_size;
    static bool configured = false;
    if (!configured) {
        cudaFuncSetAttribute(fused_decode_kernel, cudaFuncAttributeMaxDynamicSharedMemorySize, SM_TOTAL);
        configured = true;
    }
    fused_decode_kernel<<<GRID, NTHREADS, SM_TOTAL>>>(
        (const __nv_bfloat16*)d_in[0], (const char*)d_in[1], (const char*)d_in[2],
        (const __nv_bfloat16*)d_in[3], (const __nv_bfloat16*)d_in[4],
        (const __nv_bfloat16*)d_in[6], (const __nv_bfloat16*)d_in[7], (__nv_bfloat16*)d_out);
}
```

```cpp
#include <cuda_runtime.h>
#include <cuda_bf16.h>
#include <stdint.h>

namespace {

constexpr int NB = 8, NH = 16, SK = 4096, DH = 256, DM = 448, FF = 1792;
constexpr int NBH = NB * NH;
constexpr int TILE_BYTES = 32768;
constexpr int HALF_BYTES = TILE_BYTES / 2;
constexpr int TILES_PER_BH = 64;
constexpr int NKT = NBH * TILES_PER_BH;
constexpr int GRID = 132;
constexpr int NU2 = 2 * GRID;
constexpr int NUNITS = 2 * NKT - NU2;
constexpr int NDRAW = NUNITS - GRID;
constexpr int NHSL = FF / 32;
constexpr int NSRC = NBH + NHSL;
constexpr int NFIN = 112;
constexpr int NTHREADS = 15 * 32;
constexpr int DONE = 1 << 30;
constexpr float LN_EPS = 1.0013580322265625e-05f;

constexpr int NSLOT = 5;
constexpr int CAPH = 3;
constexpr int PF_AT = 4;
constexpr int H_START = 1000, CLR_START = 1600, SM_MARGIN = 1200, RED_MARGIN = 4 * GRID;

constexpr int XN_PITCH = 456;
constexpr int WS_PITCH = 80;
constexpr int RUN_PITCH = 4 * 896 + 16;
constexpr int RED_PITCH = 160;
constexpr int SM_RING = 0;
constexpr int SM_SIDE = SM_RING + NSLOT * TILE_BYTES;
constexpr int SM_STAGE = SM_SIDE + NSLOT * 1024;
constexpr int SM_Q0 = SM_STAGE + 4 * 512;
constexpr int SM_WS = SM_Q0 + 2048;
constexpr int SM_RED = SM_WS + DM * WS_PITCH;
constexpr int SM_XN = SM_RED + 7 * 8 * RED_PITCH;
constexpr int SM_MISC = SM_XN + NB * XN_PITCH * 2;
constexpr int SM_TOTAL = SM_MISC + 6656;

struct Misc {
    unsigned long long full[2 * NSLOT];
    unsigned long long empty[NSLOT];
    unsigned long long wobar, auxbar;
    int desc[NSLOT];
    int progress;
    float hred[2][4];
    float fin[2][4][32];
    __align__(16) float hsm[2][8][40];
    __align__(16) float osm[2][8][40];
};

static_assert(sizeof(Misc) <= 6656 && SM_MISC % 16 == 0 && SM_TOTAL <= 227 * 1024, "smem layout");

__device__ unsigned g_ticket;
__device__ unsigned g_epoch;
__device__ __align__(128) unsigned g_q[NBH * DH];
__device__ __align__(128) unsigned g_sp[NBH * SK];
__device__ __align__(128) unsigned g_rec[NKT * DH];
__device__ __align__(128) unsigned g_pp[NFIN * NSRC * 32];


__device__ __forceinline__ uint32_t smem_u32(const void* p) { return (uint32_t)__cvta_generic_to_shared(p); }
__device__ __forceinline__ void mbar_init(uint32_t bar, uint32_t cnt) {
    asm volatile("mbarrier.init.shared::cta.b64 [%0], %1;" ::"r"(bar), "r"(cnt) : "memory");
}
__device__ __forceinline__ void mbar_expect_tx(uint32_t bar, uint32_t bytes) {
    asm volatile("mbarrier.arrive.expect_tx.shared::cta.b64 _, [%0], %1;" ::"r"(bar), "r"(bytes) : "memory");
}
__device__ __forceinline__ void mbar_arrive(uint32_t bar) {
    asm volatile("mbarrier.arrive.shared::cta.b64 _, [%0];" ::"r"(bar) : "memory");
}
__device__ __forceinline__ bool mbar_try(uint32_t bar, uint32_t parity) {
    uint32_t done;
    asm volatile("{\n.reg .pred p;\nmbarrier.try_wait.parity.shared::cta.b64 p, [%1], %2;\nselp.u32 %0, 1, 0, p;\n}"
                 : "=r"(done) : "r"(bar), "r"(parity) : "memory");
    return done != 0;
}
constexpr long long SPIN_LIMIT = 4000000000LL;
struct Watchdog {
    long long t0;
    __device__ __forceinline__ Watchdog() { t0 = clock64(); }
    __device__ __forceinline__ void check() { if (clock64() - t0 > SPIN_LIMIT) __trap(); }
};
__device__ __forceinline__ void mbar_wait(uint32_t bar, uint32_t parity) {
    if (mbar_try(bar, parity)) return;
    Watchdog wd;
    while (!mbar_try(bar, parity)) wd.check();
}
__device__ __forceinline__ void bulk_load(uint32_t dst, const void* src, uint32_t bytes, uint32_t bar) {
    asm volatile("cp.async.bulk.shared::cluster.global.mbarrier::complete_tx::bytes [%0], [%1], %2, [%3];"
                 ::"r"(dst), "l"(src), "r"(bytes), "r"(bar) : "memory");
}
__device__ __forceinline__ void bulk_load_hint(uint32_t dst, const void* src, uint32_t bytes, uint32_t bar, uint64_t pol) {
    asm volatile("cp.async.bulk.shared::cluster.global.mbarrier::complete_tx::bytes.L2::cache_hint [%0], [%1], %2, [%3], %4;"
                 ::"r"(dst), "l"(src), "r"(bytes), "r"(bar), "l"(pol) : "memory");
}
__device__ __forceinline__ void bar_sync(int id, int n) { asm volatile("bar.sync %0, %1;" ::"r"(id), "r"(n) : "memory"); }
__device__ __forceinline__ uint4 lds128(uint32_t a) {
    uint4 v;
    asm volatile("ld.shared.v4.u32 {%0,%1,%2,%3}, [%4];" : "=r"(v.x), "=r"(v.y), "=r"(v.z), "=r"(v.w) : "r"(a));
    return v;
}
__device__ __forceinline__ uint2 lds64(uint32_t a) {
    uint2 v;
    asm volatile("ld.shared.v2.u32 {%0,%1}, [%2];" : "=r"(v.x), "=r"(v.y) : "r"(a));
    return v;
}
__device__ __forceinline__ uint32_t lds32(uint32_t a) {
    uint32_t v;
    asm volatile("ld.shared.u32 %0, [%1];" : "=r"(v) : "r"(a));
    return v;
}
__device__ __forceinline__ void sts128(uint32_t a, uint4 v) {
    asm volatile("st.shared.v4.u32 [%0], {%1,%2,%3,%4};" ::"r"(a), "r"(v.x), "r"(v.y), "r"(v.z), "r"(v.w) : "memory");
}
__device__ __forceinline__ void ldsm4t(uint32_t (&r)[4], uint32_t a) {
    asm volatile("ldmatrix.sync.aligned.m8n8.x4.trans.shared.b16 {%0,%1,%2,%3}, [%4];"
                 : "=r"(r[0]), "=r"(r[1]), "=r"(r[2]), "=r"(r[3]) : "r"(a));
}
__device__ __forceinline__ void mma16816(float (&d)[4], uint32_t a0, uint32_t a1, uint32_t a2, uint32_t a3, uint32_t b0, uint32_t b1) {
    asm volatile("mma.sync.aligned.m16n8k16.row.col.f32.bf16.bf16.f32 {%0,%1,%2,%3}, {%4,%5,%6,%7}, {%8,%9}, {%0,%1,%2,%3};"
                 : "+f"(d[0]), "+f"(d[1]), "+f"(d[2]), "+f"(d[3]) : "r"(a0), "r"(a1), "r"(a2), "r"(a3), "r"(b0), "r"(b1));
}
__device__ __forceinline__ uint4 ldg_poll128(const unsigned* p) {
    uint4 v;
    asm volatile("ld.relaxed.gpu.global.v4.u32 {%0,%1,%2,%3}, [%4];" : "=r"(v.x), "=r"(v.y), "=r"(v.z), "=r"(v.w) : "l"(p) : "memory");
    return v;
}
__device__ __forceinline__ unsigned ldg_poll32(const unsigned* p) {
    unsigned v;
    asm volatile("ld.relaxed.gpu.global.u32 %0, [%1];" : "=r"(v) : "l"(p) : "memory");
    return v;
}
__device__ __forceinline__ void stg_pub32(unsigned* p, unsigned v) {
    asm volatile("st.relaxed.gpu.global.u32 [%0], %1;" ::"l"(p), "r"(v) : "memory");
}
__device__ __forceinline__ void stg_pub64(unsigned* p, unsigned a, unsigned b) {
    asm volatile("st.relaxed.gpu.global.v2.u32 [%0], {%1,%2};" ::"l"(p), "r"(a), "r"(b) : "memory");
}
__device__ __forceinline__ void stg_pub128(unsigned* p, uint4 v) {
    asm volatile("st.relaxed.gpu.global.v4.u32 [%0], {%1,%2,%3,%4};" ::"l"(p), "r"(v.x), "r"(v.y), "r"(v.z), "r"(v.w) : "memory");
}
__device__ __forceinline__ unsigned bf16_hi(float f) {
    unsigned r;
    asm("cvt.rn.bf16x2.f32 %0, %1, %2;" : "=r"(r) : "f"(f), "f"(0.f));
    return r;
}
__device__ __forceinline__ float bf16_round(float f) { return __uint_as_float(bf16_hi(f)); }
__device__ __forceinline__ float hi_f(unsigned w) { return __uint_as_float(w & 0xffff0000u); }
__device__ __forceinline__ float lo_f(unsigned w) { return __uint_as_float(w << 16); }
__device__ __forceinline__ unsigned tagged(uint4 v, unsigned tag) { return (v.x & v.y & v.z) & (v.w & tag); }
template <int N, class F>
__device__ __forceinline__ void poll_pieces(uint4 (&v)[N], unsigned (&m)[N], unsigned tag, unsigned sleep_ns, F addr) {
    Watchdog wd;
    while (true) {
#pragma unroll
        for (int i = 0; i < N; i++) if (m[i] == 0) v[i] = ldg_poll128(addr(i));
        unsigned all = tag;
#pragma unroll
        for (int i = 0; i < N; i++) { m[i] = tagged(v[i], tag); all &= m[i]; }
        if (__all_sync(0xffffffffu, all != 0)) break;
        if (sleep_ns) __nanosleep(sleep_ns);
        wd.check();
    }
}
__device__ __forceinline__ void wait_progress(const Misc* ms, int target) {
    const volatile int* p = &ms->progress;
    if (*p >= target) return;
    Watchdog wd;
    while (*p < target) { __nanosleep(256); wd.check(); }
}

__device__ __forceinline__ void proj_load(uint32_t ws, const __nv_bfloat16* W, int pitch, int at) {
    const __nv_bfloat16* p = W + (size_t)(at >> 2) * pitch + 8 * (at & 3);
    const uint32_t d = ws + (at >> 2) * WS_PITCH + (at & 3) * 16;
#pragma unroll
    for (int i = 0; i < 7; i++)
        asm volatile("cp.async.cg.shared.global [%0], [%1], 16;" ::"r"(d + i * 64 * WS_PITCH), "l"(p + (size_t)(64 * i) * pitch) : "memory");
    asm volatile("cp.async.commit_group;" ::: "memory");
}
__device__ __forceinline__ void proj_mma(uint32_t ws, uint32_t xn_s, uint32_t red_s, int aw, int lane) {
    const int g = lane >> 2, t = lane & 3;
    float d[4][4];
#pragma unroll
    for (int n = 0; n < 4; n++)
#pragma unroll
        for (int e = 0; e < 4; e++) d[n][e] = 0.f;
    const uint32_t xa = xn_s + (g * XN_PITCH + 64 * aw + 2 * t) * 2;
    const uint32_t wa = ws + (64 * aw + (lane & 15)) * WS_PITCH + (lane >> 4) * 16;
#pragma unroll
    for (int ks = 0; ks < 4; ks++) {
        const uint32_t a0 = lds32(xa + ks * 32), a2 = lds32(xa + ks * 32 + 16);
        uint32_t b0[4], b1[4];
        ldsm4t(b0, wa + ks * 16 * WS_PITCH);
        ldsm4t(b1, wa + ks * 16 * WS_PITCH + 32);
        mma16816(d[0], a0, 0u, a2, 0u, b0[0], b0[1]);
        mma16816(d[1], a0, 0u, a2, 0u, b0[2], b0[3]);
        mma16816(d[2], a0, 0u, a2, 0u, b1[0], b1[1]);
        mma16816(d[3], a0, 0u, a2, 0u, b1[2], b1[3]);
    }
    const uint32_t ra = red_s + (aw * 8 + g) * RED_PITCH + t * 8;
#pragma unroll
    for (int n = 0; n < 4; n++)
        asm volatile("st.shared.v2.f32 [%0], {%1,%2};" ::"r"(ra + n * 32), "f"(d[n][0]), "f"(d[n][1]) : "memory");
}
__device__ __forceinline__ float proj_sum(uint32_t red_s, int b, int col) {
    float s = 0.f;
#pragma unroll
    for (int w = 0; w < 7; w++) s += __uint_as_float(lds32(red_s + (w * 8 + b) * RED_PITCH + col * 4));
    return s;
}

__device__ __noinline__ void proj2(uint32_t rows_s, uint32_t a_s, int src, int w4, unsigned keep, unsigned tg, uint32_t wbar, bool act_last) {
    const int lane = threadIdx.x & 31, g = lane >> 2, t = lane & 3;
    uint32_t wa[14][4], bb[4];
    uint32_t ra = rows_s + (lane & 7) * RUN_PITCH + (lane >> 4) * 896 + ((lane >> 3) & 1) * 16 + w4 * 224;
    uint32_t aa = a_s + g * 160 + t * 8;
    unsigned* dst = g_pp + ((28 * w4 + (g >> 2)) * NSRC + src) * 32 + (g & 3) * 8 + 2 * t;
    asm volatile("" : "+l"(dst), "+r"(ra), "+r"(aa));
#pragma unroll 1
    for (int step = 0; step < 2; step++) {
        if ((step == 0) == act_last) {
            if (wbar) mbar_wait(wbar, 0);
#pragma unroll
            for (int i = 0; i < 14; i++) ldsm4t(wa[i], ra + (i & 1) * 2 * 896 + (i >> 1) * 32);
        } else {
            if (wbar) bar_sync(5, 192);
#pragma unroll
            for (int i = 0; i < 4; i++) {
                const uint2 u = lds64(aa + i * 32), w = lds64(aa + 1280 + i * 32);
                const __nv_bfloat162 o2 = __floats2bfloat162_rn(__uint_as_float(u.x) + __uint_as_float(w.x), __uint_as_float(u.y) + __uint_as_float(w.y));
                bb[i] = *reinterpret_cast<const unsigned*>(&o2);
            }
        }
    }
    const uint32_t b0 = bb[0], b1 = bb[1], b2 = bb[2], b3 = bb[3];
    float d[7][4];
#pragma unroll
    for (int i = 0; i < 7; i++) {
        d[i][0] = d[i][1] = d[i][2] = d[i][3] = 0.f;
        mma16816(d[i], wa[2 * i][0], wa[2 * i][1], wa[2 * i][2], wa[2 * i][3], b0, b1);
    }
#pragma unroll
    for (int i = 0; i < 7; i++) mma16816(d[i], wa[2 * i + 1][0], wa[2 * i + 1][1], wa[2 * i + 1][2], wa[2 * i + 1][3], b2, b3);
#pragma unroll
    for (int i = 0; i < 7; i++) {
        stg_pub64(dst + (4 * i) * (NSRC * 32), (__float_as_uint(d[i][0]) & keep) | tg, (__float_as_uint(d[i][1]) & keep) | tg);
        stg_pub64(dst + (4 * i + 2) * (NSRC * 32), (__float_as_uint(d[i][2]) & keep) | tg, (__float_as_uint(d[i][3]) & keep) | tg);
    }
}

__global__ void __launch_bounds__(NTHREADS, 1)
fused_decode_kernel(const __nv_bfloat16* __restrict__ x, const char* __restrict__ Kc, const char* __restrict__ Vc,
                    const __nv_bfloat16* __restrict__ wq, const __nv_bfloat16* __restrict__ wo,
                    const __nv_bfloat16* __restrict__ w1, const __nv_bfloat16* __restrict__ w2,
                    __nv_bfloat16* __restrict__ out) {
    extern __shared__ __align__(1024) unsigned char smem[];
    Misc* ms = reinterpret_cast<Misc*>(smem + SM_MISC);
    const uint32_t sb = smem_u32(smem);
    const int warp = threadIdx.x >> 5, lane = threadIdx.x & 31;
    const int g = lane >> 2, t = lane & 3;
    const int cta = blockIdx.x;
    const uint32_t full0 = smem_u32(&ms->full[0]), empty0 = smem_u32(&ms->empty[0]);

    const uint32_t wobar = smem_u32(&ms->wobar), auxbar = smem_u32(&ms->auxbar);
    const int aw = warp - 4;
    const int at = threadIdx.x - 128;
    const int hs = cta < NHSL - (GRID - NBH) ? cta : cta >= NBH ? cta - (GRID - NHSL) : -1;
    const uint32_t ws_s = sb + SM_WS;

    unsigned xv[7];
    uint64_t pol = 0;
    if ((unsigned)aw < 8u) {
        if (cta < NBH) proj_load(ws_s, wq + 32 * cta, NH * DH, at);
        const unsigned* xr = reinterpret_cast<const unsigned*>(x + aw * DM);
#pragma unroll
        for (int i = 0; i < 7; i++) asm volatile("ld.global.nc.u32 %0, [%1];" : "=r"(xv[i]) : "l"(xr + lane + 32 * i));
    } else if (threadIdx.x == 384) {
        if (cta < NBH)
            asm volatile("cp.async.bulk.prefetch.L2.global [%0], %1;" ::"l"((const char*)wq + cta * 28672), "r"(28672) : "memory");
#pragma unroll
        for (int s = 0; s < NSLOT; s++) { mbar_init(full0 + 16 * s, 1); mbar_init(full0 + 16 * s + 8, 1); mbar_init(empty0 + 8 * s, 4); }
        mbar_init(wobar, 1); mbar_init(auxbar, 8);
        ms->progress = 0; ms->desc[0] = 2 * cta; ms->desc[1] = 2 * cta + 1;
        asm volatile("fence.mbarrier_init.release.cluster;" ::: "memory");
        asm volatile("fence.proxy.async.shared::cta;" ::: "memory");
        asm volatile("createpolicy.fractional.L2::evict_first.b64 %0, 1.0;" : "=l"(pol));
#pragma unroll
        for (int h = 0; h < 4; h++) mbar_expect_tx(full0 + 8 * h, HALF_BYTES);
    }
    __syncthreads();
    if (threadIdx.x == 384) {
#pragma unroll
        for (int h = 0; h < 4; h++) bulk_load_hint(sb + SM_RING + h * HALF_BYTES, Kc + (size_t)(4 * cta + h) * HALF_BYTES, HALF_BYTES, full0 + 8 * h, pol);
    }

    if (warp == 12) {
        if (lane == 0) {
            int next = (int)atomicInc(&g_ticket, NDRAW - 1);
            int unit = GRID + cta, j = 0, nu = 1;
            int hslot = 4; uint32_t eph = 1;
            int aslot = 4 - CAPH; uint32_t aph = 0;
#pragma unroll 1
            for (;;) {
                const int slot = hslot >> 1, hf = j & 1;
                uint32_t bar = full0 + 8 * hslot, bytes = HALF_BYTES, sbytes = 0, dst = sb + SM_RING + hslot * HALF_BYTES;
                int nrun = 1, s2 = 0, s1 = 0, desc = unit < NU2 ? unit * 2 + (j >> 1) : unit + NU2;
                const bool one = unit >= NU2 && unit < NUNITS;
                const bool lastj = j == (unit >= NU2 ? 1 : 3);
                const char* src;
                const unsigned* ssrc = g_q;
                if (j == 0) *(volatile int*)&ms->progress = unit < NUNITS ? desc : DONE;
                if (desc < NKT) {
                    src = Kc + (size_t)(2 * desc + hf) * HALF_BYTES;
                    if (j == 0 && one) { sbytes = 1024; ssrc = g_q + (desc >> 6) * DH; }
                } else if (unit < NUNITS) {
                    src = Vc + (size_t)(2 * (desc - NKT) + hf) * HALF_BYTES;
                    if (j == 0) { sbytes = 256; ssrc = g_sp + (desc - NKT) * 64; }
                } else {
                    bytes = 4 * DM * 2;
                    if (j == 1) {
                        nrun = cta < NBH ? 8 : 0; bar = wobar; dst = ws_s;
                        src = (const char*)(wo + (size_t)(64 * (cta >> 1) + 4 * (cta & 1)) * DM); s2 = 16 * DM * 2; s1 = 8 * DM * 2;
                    } else {
                        nrun = hs >= 0 ? 8 : 0; desc = hs >= 0 ? -2 : -1;
                        src = (const char*)(w2 + (size_t)(32 * hs) * DM); s2 = 8 * DM * 2; s1 = 4 * DM * 2;
                        mbar_wait(auxbar, 0);
                    }
                }
                if (hf == 0) { mbar_wait(empty0 + 8 * slot, eph); ms->desc[slot] = desc; }
                mbar_expect_tx(bar, nrun * bytes + sbytes);
                if (sbytes) bulk_load(sb + SM_SIDE + slot * 1024, ssrc, sbytes, bar);
                mbar_wait(full0 + 8 * aslot, aph);
                if (one && j == 1) next = (int)atomicInc(&g_ticket, NDRAW - 1);
#pragma unroll 1
                for (int r = 0; r < nrun; r++)
                    bulk_load_hint(dst + r * RUN_PITCH, src + (r >> 1) * s2 + (r & 1) * s1, bytes, bar, pol);
                if (++hslot == 2 * NSLOT) { hslot = 0; eph ^= 1; }
                if (++aslot == 2 * NSLOT) { aslot = 0; aph ^= 1; }
                j++;
                if (lastj) {
                    if (unit >= NUNITS) break;
                    if (++nu == PF_AT && cta < 128)
                        asm volatile("cp.async.bulk.prefetch.L2.global [%0], %1;" ::"l"((const char*)w1 + cta * 12544), "r"(12544) : "memory");
                    unit = next + 2 * GRID;
                    j = 0;
                }
            }
        }
        return;
    }

    if (warp >= 13) {
        if (cta >= NBH) return;
        const unsigned tag = 1u + (*(volatile unsigned*)&g_epoch & 1u);
        const int rw = warp - 13;
#pragma unroll 1
        for (int b = 0; b < NB; b++) {
            const int bh = b * NH + (cta >> 3);
            wait_progress(ms, NKT + (bh + 1) * TILES_PER_BH + RED_MARGIN);
            const unsigned* rp = g_rec + (size_t)(bh * TILES_PER_BH + 32 * rw + (lane >> 3)) * DH + 32 * (cta & 7) + 4 * (lane & 7);
            uint4 v[8];
            unsigned m[8] = {0u, 0u, 0u, 0u, 0u, 0u, 0u, 0u};
            uint32_t oa = smem_u32(&ms->osm[rw][b][4 * (lane & 7)]);
            asm volatile("" : "+r"(oa));
            poll_pieces<8>(v, m, tag, 0, [&](int i) { return rp + i * 4 * DH; });
#define UNT(w) __uint_as_float((w) & ~3u)
#define SUM8(c) (((UNT(v[0].c) + UNT(v[1].c)) + (UNT(v[2].c) + UNT(v[3].c))) + ((UNT(v[4].c) + UNT(v[5].c)) + (UNT(v[6].c) + UNT(v[7].c))))
            float s0 = SUM8(x), s1 = SUM8(y), s2 = SUM8(z), s3 = SUM8(w);
#pragma unroll
            for (int o = 8; o <= 16; o <<= 1) {
                s0 += __shfl_xor_sync(0xffffffffu, s0, o); s1 += __shfl_xor_sync(0xffffffffu, s1, o);
                s2 += __shfl_xor_sync(0xffffffffu, s2, o); s3 += __shfl_xor_sync(0xffffffffu, s3, o);
            }
            sts128(oa, make_uint4(__float_as_uint(s0), __float_as_uint(s1), __float_as_uint(s2), __float_as_uint(s3)));
        }
        asm volatile("bar.arrive 5, 192;" ::: "memory");
        return;
    }

    if (warp < 4) {
        unsigned tag = 1u + (ldg_poll32(&g_epoch) & 1u);
        asm volatile("" : "+r"(tag));
        const uint32_t stage = sb + SM_STAGE + warp * 512;
        int slot = 0, d; uint32_t ph = 0;
        {
            const uint32_t koffA = warp * 8192 + g * 512 + (t + 4 * (g & 1)) * 16;
            const uint32_t qoffA = (t + 4 * (g & 1)) * 16;
            const unsigned* q0src = g_q + ((cta + (warp >> 1) * GRID) >> 5) * DH + (warp & 1) * 128 + lane * 4;
            uint4 c0 = ldg_poll128(q0src), c1;
            uint32_t Q[32];
#pragma unroll 1
            for (int it = 0;; it++) {
                mbar_wait(full0 + 16 * slot, ph);
                d = *(volatile int*)&ms->desc[slot];
                if ((unsigned)d >= (unsigned)NKT) break;
                if (warp >= 2) mbar_wait(full0 + 16 * slot + 8, ph);
                const bool newq = it >= 4 || (it & 1) == 0;
                const uint32_t ka = sb + SM_RING + slot * TILE_BYTES + koffA, kb = ka ^ 64;
                uint4 X[4], Y[4], Z[4], W[4];
#pragma unroll
                for (int j = 0; j < 4; j++) {
                    X[j] = lds128(ka + j * 128); Y[j] = lds128(ka + j * 128 + 4096);
                    Z[j] = lds128(kb + j * 128); W[j] = lds128(kb + j * 128 + 4096);
                }
                if (newq && it > 0) {
                    const uint32_t side = it == 2 ? sb + SM_Q0 + 1024 : sb + SM_SIDE + slot * 1024;
                    c0 = lds128(side + lane * 16); c1 = lds128(side + 512 + lane * 16);
                }
                __syncwarp();
                if (lane == 0) mbar_arrive(empty0 + 8 * slot);
                if (it == 0) {
                    Watchdog wd;
                    while (!__all_sync(0xffffffffu, tagged(c0, tag) != 0)) {
                        wd.check();
                        c0 = ldg_poll128(q0src);
                    }
                    sts128(sb + SM_Q0 + warp * 512 + lane * 16, c0);
                    bar_sync(6, 128);
                    c0 = lds128(sb + SM_Q0 + lane * 16); c1 = lds128(sb + SM_Q0 + 512 + lane * 16);
                }
                if (newq) {
                    if (!__all_sync(0xffffffffu, (tagged(c0, tag) & tagged(c1, tag)) != 0)) {
                        const unsigned* src = g_q + (d >> 6) * DH + lane * 4;
                        Watchdog wd;
                        while (true) {
                            c0 = ldg_poll128(src); c1 = ldg_poll128(src + 128);
                            if (__all_sync(0xffffffffu, (tagged(c0, tag) & tagged(c1, tag)) != 0)) break;
                            __nanosleep(100); wd.check();
                        }
                    }
                    asm volatile("st.shared.v2.u32 [%0], {%1,%2};" ::"r"(stage + lane * 8), "r"(__byte_perm(c0.x, c0.y, 0x7632)), "r"(__byte_perm(c0.z, c0.w, 0x7632)) : "memory");
                    asm volatile("st.shared.v2.u32 [%0], {%1,%2};" ::"r"(stage + 256 + lane * 8), "r"(__byte_perm(c1.x, c1.y, 0x7632)), "r"(__byte_perm(c1.z, c1.w, 0x7632)) : "memory");
                    __syncwarp();
#pragma unroll
                    for (int j = 0; j < 4; j++) {
#pragma unroll
                        for (int u = 0; u < 2; u++) {
                            const uint4 qq = lds128(stage + ((qoffA ^ (u * 64)) + j * 128));
                            Q[8 * j + 4 * u + 0] = qq.x; Q[8 * j + 4 * u + 1] = qq.y;
                            Q[8 * j + 4 * u + 2] = qq.z; Q[8 * j + 4 * u + 3] = qq.w;
                        }
                    }
                }
                float d0[4] = {0.f, 0.f, 0.f, 0.f}, d1[4] = {0.f, 0.f, 0.f, 0.f};
                float d2[4] = {0.f, 0.f, 0.f, 0.f}, d3[4] = {0.f, 0.f, 0.f, 0.f};
#pragma unroll
                for (int j = 0; j < 4; j++) {
                    mma16816(d0, X[j].x, Y[j].x, X[j].y, Y[j].y, Q[8 * j + 0], Q[8 * j + 1]);
                    mma16816(d1, X[j].z, Y[j].z, X[j].w, Y[j].w, Q[8 * j + 2], Q[8 * j + 3]);
                    mma16816(d2, Z[j].x, W[j].x, Z[j].y, W[j].y, Q[8 * j + 4], Q[8 * j + 5]);
                    mma16816(d3, Z[j].z, W[j].z, Z[j].w, W[j].w, Q[8 * j + 6], Q[8 * j + 7]);
                }
                float s[4];
#pragma unroll
                for (int e = 0; e < 4; e++) s[e] = (d0[e] + d1[e]) + (d2[e] + d3[e]);
                const float slo = (g & 1) ? s[1] : s[0], shi = (g & 1) ? s[3] : s[2];
                if (t < 2) stg_pub32(g_sp + d * 64 + 16 * warp + 8 * t + g, bf16_hi(t ? shi : slo) | tag);
                if (++slot == NSLOT) { slot = 0; ph ^= 1; }
            }
        }
        {
            const unsigned tagP = tag << 2;
            const int mi = lane >> 3, r = lane & 7;
            const uint32_t voff = (r + 8 * (mi >> 1)) * 512 + 128 * warp + (((mi & 1) ^ r) * 16);
            const uint32_t psel = (t == (g >> 1)) ? ((g & 1) ? 0x3244u : 0x4432u) : 0x4444u;
#pragma unroll 1
            while (d >= 0) {
                const int vt = d - NKT;
                const uint32_t va = sb + SM_RING + slot * TILE_BYTES + voff, side = sb + SM_SIDE + slot * 1024;
                uint32_t pb[8], A[8][4];
#pragma unroll
                for (int kg = 0; kg < 8; kg++) pb[kg] = lds32(side + (8 * kg + g) * 4);
#pragma unroll
                for (int k = 0; k < 8; k++) ldsm4t(A[k], (va ^ (32 * (k & 3))) + (k >> 2) * 8192);
                unsigned ok = ((pb[0] & pb[1] & pb[2]) & (pb[3] & pb[4] & pb[5])) & (pb[6] & pb[7] & tagP);
                if (!__all_sync(0xffffffffu, ok != 0)) {
                    Watchdog wd;
                    do {
                        __nanosleep(100); wd.check();
                        ok = tagP;
#pragma unroll
                        for (int kg = 0; kg < 8; kg++) { pb[kg] = ldg_poll32(g_sp + vt * 64 + 8 * kg + g); ok &= pb[kg]; }
                    } while (!__all_sync(0xffffffffu, ok != 0));
                }
#pragma unroll
                for (int kg = 0; kg < 8; kg++) pb[kg] = __byte_perm(pb[kg], 0, psel);
                float acc[4][4];
#pragma unroll
                for (int i = 0; i < 4; i++)
#pragma unroll
                    for (int e = 0; e < 4; e++) acc[i][e] = 0.f;
#pragma unroll
                for (int k = 0; k < 8; k++) mma16816(acc[k & 3], A[k][0], A[k][1], A[k][2], A[k][3], pb[2 * (k >> 2)], pb[2 * (k >> 2) + 1]);
                mbar_wait(full0 + 16 * slot + 8, ph);
#pragma unroll
                for (int k = 0; k < 8; k++) ldsm4t(A[k], (va ^ (32 * (k & 3))) + (2 + (k >> 2)) * 8192);
#pragma unroll
                for (int k = 0; k < 8; k++) mma16816(acc[k & 3], A[k][0], A[k][1], A[k][2], A[k][3], pb[4 + 2 * (k >> 2)], pb[5 + 2 * (k >> 2)]);
                {
                    float e0[4], e1[4];
#pragma unroll
                    for (int i = 0; i < 4; i++) { e0[i] = acc[i][0] + acc[i][3]; e1[i] = acc[i][1] + acc[i][2]; }
                    e0[0] += __shfl_xor_sync(0xffffffffu, e0[1], 1);
                    e1[0] += __shfl_xor_sync(0xffffffffu, e1[1], 1);
                    e0[2] += __shfl_xor_sync(0xffffffffu, e0[3], 1);
                    e1[2] += __shfl_xor_sync(0xffffffffu, e1[3], 1);
                    e0[0] += __shfl_xor_sync(0xffffffffu, e0[2], 2);
                    e1[0] += __shfl_xor_sync(0xffffffffu, e1[2], 2);
                    stg_pub64(g_rec + (size_t)vt * DH + 64 * warp + 2 * lane,
                              (__float_as_uint(e0[0]) & ~3u) | tag, (__float_as_uint(e1[0]) & ~3u) | tag);
                }
                if (lane == 0) mbar_arrive(empty0 + 8 * slot);
                if (++slot == NSLOT) { slot = 0; ph ^= 1; }
                mbar_wait(full0 + 16 * slot, ph);
                d = *(volatile int*)&ms->desc[slot];
            }
        }
        if (d == -2) proj2(sb + SM_RING + slot * TILE_BYTES, smem_u32(&ms->hsm[0][0][0]), NBH + hs, warp, ~3u, tag, 0u, false);
        return;
    }

    const uint32_t xn_s = sb + SM_XN, red_s = sb + SM_RED;
    const unsigned ep = *(volatile unsigned*)&g_epoch;
#pragma unroll 1
    for (int job = 1; job < 3; job++) {
        if (job == 1) {
            float s = 0.f;
#pragma unroll
            for (int i = 0; i < 7; i++) s += lo_f(xv[i]) + hi_f(xv[i]);
#pragma unroll
            for (int o = 16; o; o >>= 1) s += __shfl_xor_sync(0xffffffffu, s, o);
            const float mean = s * (1.0f / DM);
            float v = 0.f;
#pragma unroll
            for (int i = 0; i < 7; i++) {
                const float a = lo_f(xv[i]) - mean, b = hi_f(xv[i]) - mean;
                v += a * a + b * b;
            }
#pragma unroll
            for (int o = 16; o; o >>= 1) v += __shfl_xor_sync(0xffffffffu, v, o);
            const float mb = bf16_round(mean);
            float sd, rinv;
            asm("sqrt.approx.f32 %0, %1;" : "=f"(sd) : "f"(bf16_round(bf16_round(v * (1.0f / DM)) + LN_EPS)));
            asm("rcp.approx.f32 %0, %1;" : "=f"(rinv) : "f"(bf16_round(sd)));
#pragma unroll
            for (int i = 0; i < 7; i++) {
                const __nv_bfloat162 df = __floats2bfloat162_rn(lo_f(xv[i]) - mb, hi_f(xv[i]) - mb);
                const unsigned du = *reinterpret_cast<const unsigned*>(&df);
                const __nv_bfloat162 xn = __floats2bfloat162_rn(lo_f(du) * rinv, hi_f(du) * rinv);
                asm volatile("st.shared.u32 [%0], %1;" ::"r"(xn_s + aw * XN_PITCH * 2 + (lane + 32 * i) * 4), "r"(*reinterpret_cast<const unsigned*>(&xn)) : "memory");
            }
        }
        if (job == 2) {
            if (hs < 0) break;
            wait_progress(ms, H_START);
            proj_load(ws_s, w1 + 32 * hs, FF, at);
        }
        asm volatile("cp.async.wait_group 0;" ::: "memory");
        bar_sync(2, 256);
        if (aw < 7) proj_mma(ws_s, xn_s, red_s, aw, lane);
        bar_sync(2, 256);
        const float pv = bf16_round(proj_sum(red_s, aw, lane));
        if (job == 1 && cta < NBH) stg_pub32(g_q + aw * (NH * DH) + 32 * cta + lane, __float_as_uint(pv) | (1u + (ep & 1u)));
        if (job == 2) { ms->hsm[0][aw][((lane & 3) << 3) | (lane >> 2)] = __fdividef(pv, 1.0f + __expf(-pv)); ms->hsm[1][aw][lane] = 0.f; }
    }
    unsigned tag = 1u + (ep & 1u);
    asm volatile("" : "+r"(tag));
    bar_sync(2, 256);

    if (aw >= 4) {
        if (cta >= NBH) { if (lane == 0) mbar_arrive(auxbar); return; }
        const int ww = aw - 4;
        const uint32_t o_s = smem_u32(&ms->osm[0][0][0]);
        wait_progress(ms, CLR_START);
        proj2(ws_s, o_s, cta, ww, 0u, 0u, 0u, false);
        asm volatile("fence.proxy.async.shared::cta;" ::: "memory");
        __syncwarp();
        if (lane == 0) mbar_arrive(auxbar);
        proj2(ws_s, o_s, cta, ww, ~3u, tag, wobar, cta >= NBH - 16);
        return;
    }

    if (hs >= 0) {
        proj2(ws_s, smem_u32(&ms->hsm[0][0][0]), NBH + hs, aw, 0u, 0u, 0u, false);
        __threadfence();
    }
    asm volatile("fence.proxy.async.shared::cta;" ::: "memory");
    __syncwarp();
    if (lane == 0) mbar_arrive(auxbar);
    if (cta < NBH) {
        const int bh = cta;
        wait_progress(ms, (bh + 1) * TILES_PER_BH + SM_MARGIN);
#pragma unroll 4
        for (int i = 0; i < 32; i++)
            stg_pub128(g_rec + (size_t)bh * TILES_PER_BH * DH + at * 4 + i * 512, make_uint4(0u, 0u, 0u, 0u));
        __threadfence();
        unsigned* sp = g_sp + bh * SK + at * 4;
        uint4 v[8];
        unsigned vm[8] = {0u, 0u, 0u, 0u, 0u, 0u, 0u, 0u};
        poll_pieces<8>(v, vm, tag, 200, [&](int i) { return sp + i * 512; });
        float m = -INFINITY;
#pragma unroll
        for (int i = 0; i < 8; i++) m = fmaxf(fmaxf(fmaxf(m, hi_f(v[i].x)), fmaxf(hi_f(v[i].y), hi_f(v[i].z))), hi_f(v[i].w));
#pragma unroll
        for (int o = 16; o; o >>= 1) m = fmaxf(m, __shfl_xor_sync(0xffffffffu, m, o));
        if (lane == 0) ms->hred[0][aw] = m;
        bar_sync(3, 128);
        m = fmaxf(fmaxf(ms->hred[0][0], ms->hred[0][1]), fmaxf(ms->hred[0][2], ms->hred[0][3]));
        const float sc = 0.0625f * 1.4426950408889634f;
        float e[32], sum = 0.f;
#pragma unroll
        for (int i = 0; i < 8; i++) {
            e[4 * i + 0] = exp2f((hi_f(v[i].x) - m) * sc);
            e[4 * i + 1] = exp2f((hi_f(v[i].y) - m) * sc);
            e[4 * i + 2] = exp2f((hi_f(v[i].z) - m) * sc);
            e[4 * i + 3] = exp2f((hi_f(v[i].w) - m) * sc);
            sum += (e[4 * i] + e[4 * i + 1]) + (e[4 * i + 2] + e[4 * i + 3]);
        }
#pragma unroll
        for (int o = 16; o; o >>= 1) sum += __shfl_xor_sync(0xffffffffu, sum, o);
        if (lane == 0) ms->hred[1][aw] = sum;
        bar_sync(3, 128);
        sum = (ms->hred[1][0] + ms->hred[1][1]) + (ms->hred[1][2] + ms->hred[1][3]);
        const float inv = 1.0f / sum;
        const unsigned tagP = tag << 2;
#pragma unroll
        for (int i = 0; i < 8; i++)
            stg_pub128(sp + i * 512, make_uint4(bf16_hi(e[4 * i] * inv) | tagP, bf16_hi(e[4 * i + 1] * inv) | tagP,
                                                bf16_hi(e[4 * i + 2] * inv) | tagP, bf16_hi(e[4 * i + 3] * inv) | tagP));
    }
    if (cta >= NFIN) return;
    {
        const int ob = 4 * (lane & 1) + ((lane >> 2) & 2) + (lane >> 4), oc = 4 * cta + ((lane >> 1) & 3);
        const float xv0 = __bfloat162float(x[ob * DM + oc]);
        const unsigned* pa = g_pp + (cta * NSRC + 32 * aw) * 32 + 4 * lane;
        const unsigned* pf = g_pp + (cta * NSRC + NBH + 14 * aw) * 32 + 4 * lane;
        uint4 v[12];
        unsigned m[12] = {0u, 0u, 0u, 0u, 0u, 0u, 0u, 0u, 0u, 0u, 0u, 0u};
        v[11] = make_uint4(tag, tag, tag, tag);
        if (lane >= 16) m[11] = tag;
        uint32_t fa = smem_u32(&ms->fin[0][0][lane]);
        __nv_bfloat16* op = out + ob * DM + oc;
        unsigned sel = lane & 24, first = aw;
        asm volatile("" : "+r"(fa), "+l"(op), "+r"(sel), "+r"(first));
        mbar_wait(wobar, 0);
        __nanosleep(300);
        poll_pieces<12>(v, m, tag, 0, [&](int i) { return i < 8 ? pa + i * 128 : pf + (i - 8) * 128; });
#define SUM4(c) ((UNT(v[8].c) + UNT(v[9].c)) + (UNT(v[10].c) + UNT(v[11].c)))
        const float sa[4] = {SUM8(x), SUM8(y), SUM8(z), SUM8(w)}, sf[4] = {SUM4(x), SUM4(y), SUM4(z), SUM4(w)};
        const bool u8 = sel & 8, u16 = sel & 16;
        const float a0 = (u8 ? sa[2] : sa[0]) + __shfl_xor_sync(0xffffffffu, u8 ? sa[0] : sa[2], 8);
        const float a1 = (u8 ? sa[3] : sa[1]) + __shfl_xor_sync(0xffffffffu, u8 ? sa[1] : sa[3], 8);
        const float f0 = (u8 ? sf[2] : sf[0]) + __shfl_xor_sync(0xffffffffu, u8 ? sf[0] : sf[2], 8);
        const float f1 = (u8 ? sf[3] : sf[1]) + __shfl_xor_sync(0xffffffffu, u8 ? sf[1] : sf[3], 8);
        const float ap = (u16 ? a1 : a0) + __shfl_xor_sync(0xffffffffu, u16 ? a0 : a1, 16);
        const float fp = (u16 ? f1 : f0) + __shfl_xor_sync(0xffffffffu, u16 ? f0 : f1, 16);
        asm volatile("st.shared.f32 [%0], %1;" ::"r"(fa + first * 128), "f"(ap) : "memory");
        asm volatile("st.shared.f32 [%0], %1;" ::"r"(fa + first * 128 + 512), "f"(fp) : "memory");
        bar_sync(3, 128);
        if (first == 0) {
            const float av = (ap + __uint_as_float(lds32(fa + 128))) + (__uint_as_float(lds32(fa + 256)) + __uint_as_float(lds32(fa + 384)));
            const float fv = (fp + __uint_as_float(lds32(fa + 640))) + (__uint_as_float(lds32(fa + 768)) + __uint_as_float(lds32(fa + 896)));
            *reinterpret_cast<unsigned short*>(op) = (unsigned short)(bf16_hi(bf16_round(xv0 + bf16_round(av)) + bf16_round(fv)) >> 16);
            if (cta == 0 && lane == 0) *(volatile unsigned*)&g_epoch = tag;
        }
    }
}

__device__ float f_q[NB * NH * DH], f_h[NB * FF], f_o[NB * NH * DH];

__global__ void fb_proj(const __nv_bfloat16* x, const __nv_bfloat16* wq, const __nv_bfloat16* w1) {
    __shared__ float xn[NB][DM];
    const int warp = threadIdx.x >> 5, lane = threadIdx.x & 31;
    {
        float s = 0.f, v = 0.f;
        for (int i = lane; i < DM; i += 32) s += __bfloat162float(x[warp * DM + i]);
        for (int o = 16; o; o >>= 1) s += __shfl_xor_sync(0xffffffffu, s, o);
        const float mean = s / DM;
        for (int i = lane; i < DM; i += 32) { const float a = __bfloat162float(x[warp * DM + i]) - mean; v += a * a; }
        for (int o = 16; o; o >>= 1) v += __shfl_xor_sync(0xffffffffu, v, o);
        const float den = bf16_round(sqrtf(bf16_round(bf16_round(v / DM) + LN_EPS)));
        for (int i = lane; i < DM; i += 32) xn[warp][i] = bf16_round(bf16_round(__bfloat162float(x[warp * DM + i]) - bf16_round(mean)) / den);
    }
    __syncthreads();
    const int c = blockIdx.x * 32 + lane;
    const bool isq = c < NH * DH;
    const __nv_bfloat16* w = isq ? wq + c : w1 + (c - NH * DH);
    const int pitch = isq ? NH * DH : FF;
    float a = 0.f;
    for (int k = 0; k < DM; k++) a = fmaf(xn[warp][k], __bfloat162float(w[(size_t)k * pitch]), a);
    a = bf16_round(a);
    if (isq) f_q[warp * NH * DH + c] = a;
    else f_h[warp * FF + c - NH * DH] = bf16_round(a / (1.0f + expf(-a)));
}
__global__ void fb_attn(const __nv_bfloat16* K, const __nv_bfloat16* V) {
    __shared__ float sc[SK], red[8];
    const int bh = blockIdx.x, warp = threadIdx.x >> 5, lane = threadIdx.x & 31;
    for (int k = warp; k < SK; k += 8) {
        float a = 0.f;
        for (int i = lane; i < DH; i += 32) a = fmaf(f_q[bh * DH + i], __bfloat162float(K[((size_t)bh * SK + k) * DH + i]), a);
        for (int o = 16; o; o >>= 1) a += __shfl_xor_sync(0xffffffffu, a, o);
        if (lane == 0) sc[k] = bf16_round(a) * 0.0625f;
    }
    __syncthreads();
    float m = -INFINITY, sum = 0.f;
    for (int k = lane; k < SK; k += 32) m = fmaxf(m, sc[k]);
    for (int o = 16; o; o >>= 1) m = fmaxf(m, __shfl_xor_sync(0xffffffffu, m, o));
    __syncthreads();
    for (int k = threadIdx.x; k < SK; k += 256) { const float e = expf(sc[k] - m); sc[k] = e; sum += e; }
    for (int o = 16; o; o >>= 1) sum += __shfl_xor_sync(0xffffffffu, sum, o);
    if (lane == 0) red[warp] = sum;
    __syncthreads();
    sum = 0.f;
    for (int i = 0; i < 8; i++) sum += red[i];
    float a = 0.f;
    for (int k = 0; k < SK; k++) a = fmaf(bf16_round(sc[k] / sum), __bfloat162float(V[((size_t)bh * SK + k) * DH + threadIdx.x]), a);
    f_o[bh * DH + threadIdx.x] = bf16_round(a);
}
__global__ void fb_out(const __nv_bfloat16* x, const __nv_bfloat16* wo, const __nv_bfloat16* w2, __nv_bfloat16* out) {
    const int b = blockIdx.y, c = blockIdx.x * 32 + threadIdx.x;
    float a = 0.f, f = 0.f;
    for (int k = 0; k < NH * DH; k++) a = fmaf(f_o[b * NH * DH + k], __bfloat162float(wo[(size_t)k * DM + c]), a);
    for (int k = 0; k < FF; k++) f = fmaf(f_h[b * FF + k], __bfloat162float(w2[(size_t)k * DM + c]), f);
    out[b * DM + c] = __float2bfloat16_rn(bf16_round(__bfloat162float(x[b * DM + c]) + bf16_round(a)) + bf16_round(f));
}

}

extern "C" void kernel_launch(void* const* d_in, const int* in_sizes, int n_in, void* d_out, int out_size) {
    (void)in_sizes; (void)n_in; (void)out_size;
    const __nv_bfloat16* x = (const __nv_bfloat16*)d_in[0];
    const __nv_bfloat16 *wq = (const __nv_bfloat16*)d_in[3], *wo = (const __nv_bfloat16*)d_in[4];
    const __nv_bfloat16 *w1 = (const __nv_bfloat16*)d_in[6], *w2 = (const __nv_bfloat16*)d_in[7];
    static int mode = -1;
    if (mode < 0) {
        int dev = 0, sms = 0, occ = 0;
        cudaGetDevice(&dev);
        cudaDeviceGetAttribute(&sms, cudaDevAttrMultiProcessorCount, dev);
        const cudaError_t e = cudaFuncSetAttribute(fused_decode_kernel, cudaFuncAttributeMaxDynamicSharedMemorySize, SM_TOTAL);
        if (e == cudaSuccess) cudaOccupancyMaxActiveBlocksPerMultiprocessor(&occ, fused_decode_kernel, NTHREADS, SM_TOTAL);
        (void)cudaGetLastError();
        mode = (e == cudaSuccess && sms * occ >= GRID) ? 1 : 0;
    }
    if (mode == 1) {
        fused_decode_kernel<<<GRID, NTHREADS, SM_TOTAL>>>(x, (const char*)d_in[1], (const char*)d_in[2], wq, wo, w1, w2, (__nv_bfloat16*)d_out);
    } else {
        fb_proj<<<(NH * DH + FF) / 32, 256>>>(x, wq, w1);
        fb_attn<<<NBH, 256>>>((const __nv_bfloat16*)d_in[1], (const __nv_bfloat16*)d_in[2]);
        fb_out<<<dim3(DM / 32, NB), 32>>>(x, wo, w2, (__nv_bfloat16*)d_out);
    }
}
```
